```python
import torch

def _softmax(x, axis=-1):
    return torch.softmax(x, dim=axis)
def _gelu(x):
    return torch.nn.functional.gelu(x, approximate="tanh")
def _silu(x):
    return torch.nn.functional.silu(x)
def _sigmoid(x):
    return torch.sigmoid(x)
def _layernorm(x, axis=-1, eps=1e-5):
    m = x.mean(dim=axis, keepdim=True)
    v = x.var(dim=axis, keepdim=True, unbiased=False)
    return (x - m) / torch.sqrt(v + eps)
def _scatter_add(tgt, idx, src, axis=0):
    return tgt.clone().index_add_(axis, idx, src)
def _segment_sum(src, seg, n):
    out = torch.zeros((n,) + src.shape[1:], dtype=src.dtype)
    return out.index_add_(0, seg, src)
def _pad(x, pw):
    flat = tuple(v for pair in reversed(pw) for v in pair)
    return torch.nn.functional.pad(x, flat)

kernel_name = 'standalone__self_sup_conv_stem_wavlm__speech'

def setup_inputs():

    _w = (lambda a: (lambda t: t.to(torch.bfloat16) if t.is_floating_point() else t)(torch.as_tensor(a)))
    B, T, D, K = 2, 1000, 512, 15
    scale = (K * D) ** -0.5
    return {
        "x": _w((lambda *s: torch.randn(*s, dtype=torch.bfloat16) * 0.05)(B, T, D)),
        "w": _w((lambda *s: torch.randn(*s, dtype=torch.bfloat16) * 0.05)(K, D, D) * scale),
        "gn_gamma": _w((lambda *s: torch.randn(*s, dtype=torch.bfloat16) * 0.05)(D) * 0.1 + 1.0),
        "gn_beta": _w((lambda *s: torch.randn(*s, dtype=torch.bfloat16) * 0.05)(D) * 0.1),
    }

def reference(x, w, gn_gamma, gn_beta):
    B, T, D = x.shape
    K = w.shape[0]
    s = 2
    L = (T - K) // s + 1
    h = torch.einsum('blc,cd->bld', x[:, 0:s * L:s, :], w[0])
    for i in range(1, K):
        h = h + torch.einsum('blc,cd->bld', x[:, i:i + s * L:s, :], w[i])
    mu = torch.einsum('bld->bd', h)[:, None, :] / L
    var = torch.einsum('bld->bd', (h - mu) ** 2)[:, None, :] / L
    h = (h - mu) / torch.sqrt(var + 1e-5)
    h = h * gn_gamma[None, None, :] + gn_beta[None, None, :]
    return _gelu(h)
```

```cpp
#include <cuda_runtime.h>
#include <cuda_bf16.h>
#include <cuda.h>
#include <stdint.h>
#include <type_traits>

namespace {

constexpr int kB = 2, kT = 1000, kD = 512, kL = 493;
constexpr int kN = 248;
constexpr int kStages = 8;
constexpr int kUnits = 16;
constexpr int kThreads = 256;
constexpr uint32_t kSpinLimit = 1u << 18;

constexpr uint32_t X_BYTES = 8192;
constexpr uint32_t W_BYTES = 16384;
constexpr uint32_t STAGE_BYTES = X_BYTES + W_BYTES;
constexpr uint32_t OFF_RX = kStages * STAGE_BYTES;
constexpr uint32_t OFF_XA = OFF_RX + 8192;
constexpr uint32_t OFF_MISC = OFF_XA + 16384;
constexpr uint32_t OFF_BAR = OFF_MISC + 1024;
constexpr uint32_t SMEM_BYTES = OFF_BAR + 256;
constexpr uint32_t OFF_STG = 0;
constexpr uint32_t OFF_SLOT = STAGE_BYTES;

__device__ uint4 g_part[128 * 2 * 4 * 128];
__device__ uint4 g_stat[16 * 4 * 8 * 8];
__device__ unsigned int g_epoch[128];


__device__ __forceinline__ uint32_t smem_u32(const void* p) { return (uint32_t)__cvta_generic_to_shared(p); }
__device__ __forceinline__ void mbar_init(uint32_t bar, uint32_t cnt) { asm volatile("mbarrier.init.shared::cta.b64 [%0], %1;" ::"r"(bar), "r"(cnt)); }
__device__ __forceinline__ void mbar_expect_tx(uint32_t bar, uint32_t bytes) { asm volatile("mbarrier.arrive.expect_tx.shared::cta.b64 _, [%0], %1;" ::"r"(bar), "r"(bytes) : "memory"); }
__device__ __forceinline__ void mbar_arrive(uint32_t bar) { asm volatile("mbarrier.arrive.shared::cta.b64 _, [%0];" ::"r"(bar) : "memory"); }
__device__ __forceinline__ bool mbar_try(uint32_t bar, uint32_t parity) {
    uint32_t ok;
    asm volatile("{\n.reg .pred p;\nmbarrier.try_wait.parity.shared::cta.b64 p, [%1], %2;\nselp.u32 %0, 1, 0, p;\n}\n" : "=r"(ok) : "r"(bar), "r"(parity) : "memory");
    return ok;
}
__device__ __forceinline__ void mbar_wait(uint32_t bar, uint32_t parity) {
    uint32_t it = 0;
    while (!mbar_try(bar, parity)) { if (++it > kSpinLimit) __trap(); }
}
__device__ __forceinline__ void tma_4d(uint32_t dst, const CUtensorMap* m, uint32_t bar, int c0, int c1, int c2, int c3) {
    asm volatile("cp.async.bulk.tensor.4d.shared::cluster.global.mbarrier::complete_tx::bytes [%0], [%1, {%3, %4, %5, %6}], [%2];"
                 ::"r"(dst), "l"(m), "r"(bar), "r"(c0), "r"(c1), "r"(c2), "r"(c3) : "memory");
}
__device__ __forceinline__ void tma_3d(uint32_t dst, const CUtensorMap* m, uint32_t bar, int c0, int c1, int c2) {
    asm volatile("cp.async.bulk.tensor.3d.shared::cluster.global.mbarrier::complete_tx::bytes [%0], [%1, {%3, %4, %5}], [%2];"
                 ::"r"(dst), "l"(m), "r"(bar), "r"(c0), "r"(c1), "r"(c2) : "memory");
}
__device__ __forceinline__ void cp_async16(uint32_t dst, const void* src, bool valid) {
    asm volatile("cp.async.cg.shared.global [%0], [%1], 16, %2;" ::"r"(dst), "l"(src), "r"(valid ? 16 : 0) : "memory");
}
__device__ __forceinline__ void wg_fence() { asm volatile("wgmma.fence.sync.aligned;" ::: "memory"); }
__device__ __forceinline__ void wg_commit() { asm volatile("wgmma.commit_group.sync.aligned;" ::: "memory"); }
template <int N> __device__ __forceinline__ void wg_wait() { asm volatile("wgmma.wait_group.sync.aligned %0;" ::"n"(N) : "memory"); }
__device__ __forceinline__ void bar_sync(int id, int n) { asm volatile("bar.sync %0, %1;" ::"r"(id), "r"(n) : "memory"); }
__device__ __forceinline__ void bar_arrive(int id, int n) { asm volatile("bar.arrive %0, %1;" ::"r"(id), "r"(n) : "memory"); }

template <uint32_t OA, uint32_t OB>
__device__ __forceinline__ void wgmma_n128i(float (&d)[64], uint64_t baseA, uint64_t baseB) {
    asm volatile("{\n.reg .b64 da, db;\n"
        "add.s64 da, %64, %66;\nadd.s64 db, %65, %67;\n"
        "wgmma.mma_async.sync.aligned.m64n128k16.f32.bf16.bf16 "
        "{%0, %1, %2, %3, %4, %5, %6, %7, %8, %9, %10, %11, %12, %13, %14, %15, "
        "%16, %17, %18, %19, %20, %21, %22, %23, %24, %25, %26, %27, %28, %29, %30, %31, "
        "%32, %33, %34, %35, %36, %37, %38, %39, %40, %41, %42, %43, %44, %45, %46, %47, "
        "%48, %49, %50, %51, %52, %53, %54, %55, %56, %57, %58, %59, %60, %61, %62, %63}, "
        "da, db, 1, 1, 1, 1, 0;\n}\n"
        : "+f"(d[0]), "+f"(d[1]), "+f"(d[2]), "+f"(d[3]), "+f"(d[4]), "+f"(d[5]), "+f"(d[6]), "+f"(d[7]),
          "+f"(d[8]), "+f"(d[9]), "+f"(d[10]), "+f"(d[11]), "+f"(d[12]), "+f"(d[13]), "+f"(d[14]), "+f"(d[15]),
          "+f"(d[16]), "+f"(d[17]), "+f"(d[18]), "+f"(d[19]), "+f"(d[20]), "+f"(d[21]), "+f"(d[22]), "+f"(d[23]),
          "+f"(d[24]), "+f"(d[25]), "+f"(d[26]), "+f"(d[27]), "+f"(d[28]), "+f"(d[29]), "+f"(d[30]), "+f"(d[31]),
          "+f"(d[32]), "+f"(d[33]), "+f"(d[34]), "+f"(d[35]), "+f"(d[36]), "+f"(d[37]), "+f"(d[38]), "+f"(d[39]),
          "+f"(d[40]), "+f"(d[41]), "+f"(d[42]), "+f"(d[43]), "+f"(d[44]), "+f"(d[45]), "+f"(d[46]), "+f"(d[47]),
          "+f"(d[48]), "+f"(d[49]), "+f"(d[50]), "+f"(d[51]), "+f"(d[52]), "+f"(d[53]), "+f"(d[54]), "+f"(d[55]),
          "+f"(d[56]), "+f"(d[57]), "+f"(d[58]), "+f"(d[59]), "+f"(d[60]), "+f"(d[61]), "+f"(d[62]), "+f"(d[63])
        : "l"(baseA), "l"(baseB), "n"((uint64_t)(OA >> 4)), "n"((uint64_t)(OB >> 4)));
}
template <uint32_t OA, uint32_t OB>
__device__ __forceinline__ void wgmma_n128s(float (&d)[64], uint64_t baseA, uint64_t baseB, int scaleD) {
    asm volatile("{\n.reg .pred p;\n.reg .b64 da, db;\nsetp.ne.b32 p, %68, 0;\n"
        "add.s64 da, %64, %66;\nadd.s64 db, %65, %67;\n"
        "wgmma.mma_async.sync.aligned.m64n128k16.f32.bf16.bf16 "
        "{%0, %1, %2, %3, %4, %5, %6, %7, %8, %9, %10, %11, %12, %13, %14, %15, "
        "%16, %17, %18, %19, %20, %21, %22, %23, %24, %25, %26, %27, %28, %29, %30, %31, "
        "%32, %33, %34, %35, %36, %37, %38, %39, %40, %41, %42, %43, %44, %45, %46, %47, "
        "%48, %49, %50, %51, %52, %53, %54, %55, %56, %57, %58, %59, %60, %61, %62, %63}, "
        "da, db, p, 1, 1, 1, 0;\n}\n"
        : "+f"(d[0]), "+f"(d[1]), "+f"(d[2]), "+f"(d[3]), "+f"(d[4]), "+f"(d[5]), "+f"(d[6]), "+f"(d[7]),
          "+f"(d[8]), "+f"(d[9]), "+f"(d[10]), "+f"(d[11]), "+f"(d[12]), "+f"(d[13]), "+f"(d[14]), "+f"(d[15]),
          "+f"(d[16]), "+f"(d[17]), "+f"(d[18]), "+f"(d[19]), "+f"(d[20]), "+f"(d[21]), "+f"(d[22]), "+f"(d[23]),
          "+f"(d[24]), "+f"(d[25]), "+f"(d[26]), "+f"(d[27]), "+f"(d[28]), "+f"(d[29]), "+f"(d[30]), "+f"(d[31]),
          "+f"(d[32]), "+f"(d[33]), "+f"(d[34]), "+f"(d[35]), "+f"(d[36]), "+f"(d[37]), "+f"(d[38]), "+f"(d[39]),
          "+f"(d[40]), "+f"(d[41]), "+f"(d[42]), "+f"(d[43]), "+f"(d[44]), "+f"(d[45]), "+f"(d[46]), "+f"(d[47]),
          "+f"(d[48]), "+f"(d[49]), "+f"(d[50]), "+f"(d[51]), "+f"(d[52]), "+f"(d[53]), "+f"(d[54]), "+f"(d[55]),
          "+f"(d[56]), "+f"(d[57]), "+f"(d[58]), "+f"(d[59]), "+f"(d[60]), "+f"(d[61]), "+f"(d[62]), "+f"(d[63])
        : "l"(baseA), "l"(baseB), "n"((uint64_t)(OA >> 4)), "n"((uint64_t)(OB >> 4)), "r"(scaleD));
}
template <uint32_t OA, uint32_t OB>
__device__ __forceinline__ void wgmma_n120i(float (&d)[64], uint64_t baseA, uint64_t baseB) {
    asm volatile("{\n.reg .b64 da, db;\n"
        "add.s64 da, %60, %62;\nadd.s64 db, %61, %63;\n"
        "wgmma.mma_async.sync.aligned.m64n120k16.f32.bf16.bf16 "
        "{%0, %1, %2, %3, %4, %5, %6, %7, %8, %9, %10, %11, %12, %13, %14, %15, "
        "%16, %17, %18, %19, %20, %21, %22, %23, %24, %25, %26, %27, %28, %29, %30, %31, "
        "%32, %33, %34, %35, %36, %37, %38, %39, %40, %41, %42, %43, %44, %45, %46, %47, "
        "%48, %49, %50, %51, %52, %53, %54, %55, %56, %57, %58, %59}, "
        "da, db, 1, 1, 1, 1, 0;\n}\n"
        : "+f"(d[0]), "+f"(d[1]), "+f"(d[2]), "+f"(d[3]), "+f"(d[4]), "+f"(d[5]), "+f"(d[6]), "+f"(d[7]),
          "+f"(d[8]), "+f"(d[9]), "+f"(d[10]), "+f"(d[11]), "+f"(d[12]), "+f"(d[13]), "+f"(d[14]), "+f"(d[15]),
          "+f"(d[16]), "+f"(d[17]), "+f"(d[18]), "+f"(d[19]), "+f"(d[20]), "+f"(d[21]), "+f"(d[22]), "+f"(d[23]),
          "+f"(d[24]), "+f"(d[25]), "+f"(d[26]), "+f"(d[27]), "+f"(d[28]), "+f"(d[29]), "+f"(d[30]), "+f"(d[31]),
          "+f"(d[32]), "+f"(d[33]), "+f"(d[34]), "+f"(d[35]), "+f"(d[36]), "+f"(d[37]), "+f"(d[38]), "+f"(d[39]),
          "+f"(d[40]), "+f"(d[41]), "+f"(d[42]), "+f"(d[43]), "+f"(d[44]), "+f"(d[45]), "+f"(d[46]), "+f"(d[47]),
          "+f"(d[48]), "+f"(d[49]), "+f"(d[50]), "+f"(d[51]), "+f"(d[52]), "+f"(d[53]), "+f"(d[54]), "+f"(d[55]),
          "+f"(d[56]), "+f"(d[57]), "+f"(d[58]), "+f"(d[59])
        : "l"(baseA), "l"(baseB), "n"((uint64_t)(OA >> 4)), "n"((uint64_t)(OB >> 4)));
}
template <uint32_t OA, uint32_t OB>
__device__ __forceinline__ void wgmma_n120s(float (&d)[64], uint64_t baseA, uint64_t baseB, int scaleD) {
    asm volatile("{\n.reg .pred p;\n.reg .b64 da, db;\nsetp.ne.b32 p, %64, 0;\n"
        "add.s64 da, %60, %62;\nadd.s64 db, %61, %63;\n"
        "wgmma.mma_async.sync.aligned.m64n120k16.f32.bf16.bf16 "
        "{%0, %1, %2, %3, %4, %5, %6, %7, %8, %9, %10, %11, %12, %13, %14, %15, "
        "%16, %17, %18, %19, %20, %21, %22, %23, %24, %25, %26, %27, %28, %29, %30, %31, "
        "%32, %33, %34, %35, %36, %37, %38, %39, %40, %41, %42, %43, %44, %45, %46, %47, "
        "%48, %49, %50, %51, %52, %53, %54, %55, %56, %57, %58, %59}, "
        "da, db, p, 1, 1, 1, 0;\n}\n"
        : "+f"(d[0]), "+f"(d[1]), "+f"(d[2]), "+f"(d[3]), "+f"(d[4]), "+f"(d[5]), "+f"(d[6]), "+f"(d[7]),
          "+f"(d[8]), "+f"(d[9]), "+f"(d[10]), "+f"(d[11]), "+f"(d[12]), "+f"(d[13]), "+f"(d[14]), "+f"(d[15]),
          "+f"(d[16]), "+f"(d[17]), "+f"(d[18]), "+f"(d[19]), "+f"(d[20]), "+f"(d[21]), "+f"(d[22]), "+f"(d[23]),
          "+f"(d[24]), "+f"(d[25]), "+f"(d[26]), "+f"(d[27]), "+f"(d[28]), "+f"(d[29]), "+f"(d[30]), "+f"(d[31]),
          "+f"(d[32]), "+f"(d[33]), "+f"(d[34]), "+f"(d[35]), "+f"(d[36]), "+f"(d[37]), "+f"(d[38]), "+f"(d[39]),
          "+f"(d[40]), "+f"(d[41]), "+f"(d[42]), "+f"(d[43]), "+f"(d[44]), "+f"(d[45]), "+f"(d[46]), "+f"(d[47]),
          "+f"(d[48]), "+f"(d[49]), "+f"(d[50]), "+f"(d[51]), "+f"(d[52]), "+f"(d[53]), "+f"(d[54]), "+f"(d[55]),
          "+f"(d[56]), "+f"(d[57]), "+f"(d[58]), "+f"(d[59])
        : "l"(baseA), "l"(baseB), "n"((uint64_t)(OA >> 4)), "n"((uint64_t)(OB >> 4)), "r"(scaleD));
}
template <uint32_t OB>
__device__ __forceinline__ void wgmma_rs_n64(float (&d)[32], const uint32_t (&a)[4], uint64_t baseB) {
    asm volatile("{\n.reg .b64 db;\n"
        "add.s64 db, %36, %37;\n"
        "wgmma.mma_async.sync.aligned.m64n64k16.f32.bf16.bf16 "
        "{%0, %1, %2, %3, %4, %5, %6, %7, %8, %9, %10, %11, %12, %13, %14, %15, "
        "%16, %17, %18, %19, %20, %21, %22, %23, %24, %25, %26, %27, %28, %29, %30, %31}, "
        "{%32, %33, %34, %35}, db, 1, 1, 1, 0;\n}\n"
        : "+f"(d[0]), "+f"(d[1]), "+f"(d[2]), "+f"(d[3]), "+f"(d[4]), "+f"(d[5]), "+f"(d[6]), "+f"(d[7]),
          "+f"(d[8]), "+f"(d[9]), "+f"(d[10]), "+f"(d[11]), "+f"(d[12]), "+f"(d[13]), "+f"(d[14]), "+f"(d[15]),
          "+f"(d[16]), "+f"(d[17]), "+f"(d[18]), "+f"(d[19]), "+f"(d[20]), "+f"(d[21]), "+f"(d[22]), "+f"(d[23]),
          "+f"(d[24]), "+f"(d[25]), "+f"(d[26]), "+f"(d[27]), "+f"(d[28]), "+f"(d[29]), "+f"(d[30]), "+f"(d[31])
        : "r"(a[0]), "r"(a[1]), "r"(a[2]), "r"(a[3]), "l"(baseB), "n"((uint64_t)(OB >> 4)));
}
template <uint32_t OB>
__device__ __forceinline__ void wgmma_rs_n56(float (&d)[32], const uint32_t (&a)[4], uint64_t baseB) {
    asm volatile("{\n.reg .b64 db;\n"
        "add.s64 db, %32, %33;\n"
        "wgmma.mma_async.sync.aligned.m64n56k16.f32.bf16.bf16 "
        "{%0, %1, %2, %3, %4, %5, %6, %7, %8, %9, %10, %11, %12, %13, %14, %15, "
        "%16, %17, %18, %19, %20, %21, %22, %23, %24, %25, %26, %27}, "
        "{%28, %29, %30, %31}, db, 1, 1, 1, 0;\n}\n"
        : "+f"(d[0]), "+f"(d[1]), "+f"(d[2]), "+f"(d[3]), "+f"(d[4]), "+f"(d[5]), "+f"(d[6]), "+f"(d[7]),
          "+f"(d[8]), "+f"(d[9]), "+f"(d[10]), "+f"(d[11]), "+f"(d[12]), "+f"(d[13]), "+f"(d[14]), "+f"(d[15]),
          "+f"(d[16]), "+f"(d[17]), "+f"(d[18]), "+f"(d[19]), "+f"(d[20]), "+f"(d[21]), "+f"(d[22]), "+f"(d[23]),
          "+f"(d[24]), "+f"(d[25]), "+f"(d[26]), "+f"(d[27])
        : "r"(a[0]), "r"(a[1]), "r"(a[2]), "r"(a[3]), "l"(baseB), "n"((uint64_t)(OB >> 4)));
}

__device__ __forceinline__ float rsqrt_fast(float x) {
    float r;
    asm("rsqrt.approx.ftz.f32 %0, %1;" : "=f"(r) : "f"(x));
    return r;
}
__device__ __forceinline__ float gelu_tanh_half(float hy) {
    const float u = hy * fmaf(hy * hy, 8.0f * 0.035677408136300125f, 2.0f * 0.7978845608028654f);
    float t;
    asm("tanh.approx.f32 %0, %1;" : "=f"(t) : "f"(u));
    return fmaf(hy, t, hy);
}

__device__ __forceinline__ void st_msg(uint4* p, uint32_t w0, uint32_t w1, uint32_t w2, uint32_t w3, uint32_t par) {
    asm volatile("{\n.reg .b64 a, b;\n.reg .b128 m;\nmov.b64 a, {%1, %2};\nmov.b64 b, {%3, %4};\nmov.b128 m, {a, b};\nst.relaxed.gpu.global.b128 [%0], m;\n}\n"
                 ::"l"(p), "r"((w0 & ~1u) | par), "r"(w1), "r"(w2), "r"(w3) : "memory");
}
__device__ __forceinline__ uint4 ld_msg(const uint4* p) {
    uint4 v;
    asm volatile("{\n.reg .b64 a, b;\n.reg .b128 m;\nld.relaxed.gpu.global.b128 m, [%4];\nmov.b128 {a, b}, m;\nmov.b64 {%0, %1}, a;\nmov.b64 {%2, %3}, b;\n}\n"
                 : "=r"(v.x), "=r"(v.y), "=r"(v.z), "=r"(v.w) : "l"(p) : "memory");
    return v;
}
__device__ __forceinline__ uint32_t msg_bad(const uint4& v, uint32_t par) { return v.x ^ par; }
__device__ __forceinline__ uint32_t pack2(float lo, float hi) {
    uint32_t r;
    asm("cvt.rn.bf16x2.f32 %0, %1, %2;" : "=r"(r) : "f"(hi), "f"(lo));
    return r;
}
__device__ __forceinline__ uint32_t add2(uint32_t a, uint32_t b) {
    uint32_t r;
    asm("add.rn.bf16x2 %0, %1, %2;" : "=r"(r) : "r"(a), "r"(b));
    return r;
}
__device__ __forceinline__ float bf_lo(uint32_t w) { return __uint_as_float(w << 16); }
__device__ __forceinline__ float bf_hi(uint32_t w) { return __uint_as_float(w & 0xffff0000u); }
constexpr uint32_t kPace0 = 500, kPace = 450;
constexpr uint32_t kPollDelay = 200;
constexpr int kGoAt = 25;

template <int I, int N, typename F> __device__ __forceinline__ void static_for(F&& f) {
    if constexpr (I < N) { f(std::integral_constant<int, I>{}); static_for<I + 1, N>(f); }
}
template <int HALF, uint32_t OA, uint32_t OB> __device__ __forceinline__ void wgmma_half(float (&t)[64], uint64_t da, uint64_t db) {
    if constexpr (HALF == 0) wgmma_n128i<OA, OB>(t, da, db);
    else wgmma_n120i<OA, OB + 128 * 32>(t, da, db);
}

constexpr int kTailUnits = 6;
constexpr int kMainIters = (kUnits - kTailUnits) / 2;
constexpr int kTail = kTailUnits / 2 * 15;
constexpr int kRs = 22;
constexpr int kSs = kTail - kRs;
constexpr int kStage0 = (kUnits - kTailUnits) % kStages;
__host__ __device__ constexpr uint32_t tail_unit(int i) { return (i / 15) * 2 + (i % 15 >= 8 ? 1 : 0); }
__host__ __device__ constexpr uint32_t tail_tap(int i) { return i % 15 >= 8 ? i % 15 - 8 : i % 15; }
__host__ __device__ constexpr uint32_t tail_oa(int i) { return tail_unit(i) * STAGE_BYTES + tail_tap(i) * 2048; }
__host__ __device__ constexpr uint32_t tail_ob(int i) { return tail_unit(i) * STAGE_BYTES + tail_tap(i) * 32; }

template <uint32_t OFF> __device__ __forceinline__ void ld_afrag(uint32_t (&a)[4], uint32_t base) {
    asm volatile("ldmatrix.sync.aligned.m8n8.x4.trans.shared.b16 {%0, %1, %2, %3}, [%4];"
                 : "=r"(a[0]), "=r"(a[1]), "=r"(a[2]), "=r"(a[3]) : "r"(base + OFF) : "memory");
}

template <int OWN>
__device__ __forceinline__ void tail_ab1(float (&oth)[64], float (&own)[64], uint32_t (&af)[kRs][4], uint64_t da0, uint64_t db0, uint64_t da1, uint64_t db1,
                                         uint32_t bar_full, uint32_t a_frag, uint4* gdst, uint32_t par) {
    constexpr int OTH = OWN ^ 1;
    static_for<0, kTail>([&](auto I) {
        constexpr int i = decltype(I)::value;
        wgmma_half<OTH, tail_oa(i), tail_ob(i)>(oth, da0, db0);
        if constexpr (i + 4 < kTail && tail_unit(i + 4) != tail_unit(i + 3)) mbar_wait(bar_full + 8 * (kStage0 + tail_unit(i + 4)), 1);
        if constexpr (i >= kSs) ld_afrag<tail_oa(i)>(af[i - kSs], a_frag);
    });
    wg_commit();
    static_for<0, kSs>([&](auto I) {
        constexpr int i = decltype(I)::value;
        wgmma_half<OWN, tail_oa(i), tail_ob(i)>(own, da1, db1);
        if constexpr (i == 2) { wg_commit(); wg_wait<1>(); }
        constexpr int k = i - 3;
        if constexpr (k >= 0 && k < 8) {
            constexpr int a = 8 * k;
            constexpr bool pad = OTH == 1 && k == 7;
            st_msg(gdst + (k >> 2) * 1024 + (k & 3) * 128, pack2(oth[a], oth[a + 1]), pack2(oth[a + 2], oth[a + 3]),
                   pad ? 0u : pack2(oth[a + 4], oth[a + 5]), pad ? 0u : pack2(oth[a + 6], oth[a + 7]), par);
            __syncwarp();
        }
        if constexpr (i == kGoAt) bar_arrive(6, 256);
    });
    wg_commit();
}

template <int N, uint32_t OB> __device__ __forceinline__ void wgmma_rs(float (&d)[32], const uint32_t (&a)[4], uint64_t db) {
    if constexpr (N == 64) wgmma_rs_n64<OB>(d, a, db); else wgmma_rs_n56<OB>(d, a, db);
}

template <int Q>
__device__ __forceinline__ void tail_b23(const float (&half)[64], uint32_t (&af)[kRs][4], float (&o)[32], uint64_t db0,
                                         uint32_t rdst, uint32_t rbar) {
    constexpr int P = Q ^ 1;
    constexpr int NP = P == 3 ? 56 : 64, NO = Q == 3 ? 56 : 64;
    float p[32];
    wg_wait<0>();
#pragma unroll
    for (int i = 0; i < NP / 2; i++) asm volatile("mov.b32 %0, %1;" : "=f"(p[i]) : "f"(half[32 * (P & 1) + i]));
#pragma unroll
    for (int i = 0; i < NO / 2; i++) asm volatile("mov.b32 %0, %1;" : "=f"(o[i]) : "f"(half[32 * (Q & 1) + i]));
    wg_fence();
    static_for<0, kRs>([&](auto I) {
        constexpr int i = decltype(I)::value;
        wgmma_rs<NP, tail_ob(kSs + i) + 64 * P * 32>(p, af[i], db0);
        if constexpr (kSs + i == kGoAt) bar_arrive(6, 256);
    });
    wg_commit();
    static_for<0, kRs>([&](auto I) {
        constexpr int i = decltype(I)::value;
        wgmma_rs<NO, tail_ob(kSs + i) + 64 * Q * 32>(o, af[i], db0);
        if constexpr (i == 0) { wg_commit(); wg_wait<1>(); }
        if constexpr (i >= 1 && i <= 4) {
            constexpr int k = i - 1, a = 8 * k;
            constexpr bool pad = NP == 56 && k == 3;
            asm volatile("st.async.weak.shared::cluster.mbarrier::complete_tx::bytes.v4.b32 [%0], {%1, %2, %3, %4}, [%5];"
                         ::"r"(rdst + k * 2048), "r"(pack2(p[a], p[a + 1])), "r"(pack2(p[a + 2], p[a + 3])),
                           "r"(pad ? 0u : pack2(p[a + 4], p[a + 5])), "r"(pad ? 0u : pack2(p[a + 6], p[a + 7])), "r"(rbar) : "memory");
        }
    });
    wg_commit();
}

template <int K> __device__ __forceinline__ uint64_t fresh(uint64_t d) { return d + (uint64_t)(blockIdx.y * K); }

template <typename T> __device__ __forceinline__ T pin(T v) {
    if constexpr (sizeof(T) == 8) asm volatile("" : "+l"(v)); else asm volatile("" : "+r"(v));
    return v;
}

__device__ __forceinline__ void mbar_wait_peer(uint32_t bar, uint32_t parity) {
    uint32_t it = 0, ok;
    do {
        asm volatile("{\n.reg .pred p;\nmbarrier.try_wait.parity.relaxed.cluster.shared::cta.b64 p, [%1], %2;\nselp.u32 %0, 1, 0, p;\n}\n" : "=r"(ok) : "r"(bar), "r"(parity) : "memory");
        if (++it > kSpinLimit) __trap();
    } while (!ok);
    asm volatile("fence.acquire.sync_restrict::shared::cluster.cluster;" ::: "memory");
}

template <int NC_OWN>
__device__ __forceinline__ void finish_sums(const float (&o)[32], float (&v)[32], const uint4* xa) {
    float t[32];
    bar_sync(1, 256);
#pragma unroll
    for (int k = 0; k < 4; k++) {
        const uint4 a = xa[k * 128];
        t[8 * k] = bf_lo(a.x); t[8 * k + 1] = bf_hi(a.x); t[8 * k + 2] = bf_lo(a.y); t[8 * k + 3] = bf_hi(a.y);
        t[8 * k + 4] = bf_lo(a.z); t[8 * k + 5] = bf_hi(a.z); t[8 * k + 6] = bf_lo(a.w); t[8 * k + 7] = bf_hi(a.w);
    }
    wg_wait<0>();
#pragma unroll
    for (int i = 0; i < 32; i++) v[i] = i < 4 * NC_OWN ? o[i] + t[i] : 0.f;
}

struct Params {
    const __nv_bfloat16* x; const __nv_bfloat16* w; const __nv_bfloat16* gamma; const __nv_bfloat16* beta;
    __nv_bfloat16* out; uint4* part; uint4* stat; unsigned int* epoch;
    uint64_t descA, descB;
};

__global__ void __cluster_dims__(2, 1, 1) __launch_bounds__(kThreads, 1)
conv_stem_kernel(const Params prm, const __grid_constant__ CUtensorMap mapX, const __grid_constant__ CUtensorMap mapWe,
                 const __grid_constant__ CUtensorMap mapWo) {
    extern __shared__ __align__(1024) uint8_t smem[];
    const uint32_t sb = smem_u32(smem);
    const int tid = threadIdx.x, lane = tid & 31;
    const int q = blockIdx.x & 3;
    const int h = (blockIdx.x >> 2) & 1;
    const int j = (blockIdx.x >> 3) & 7;
    const int b = blockIdx.x >> 6;
    const int c0 = q * 128, l0 = h * kN, d0 = j * 64;
    const uint32_t bar_full = sb + OFF_BAR, bar_empty = bar_full + 8 * kStages, bar_rx = bar_empty + 8 * kStages;

    if (tid >= 128) {
        if (tid >= 160) {
            const int wq = tid >> 5, r0 = 2 * (wq - 4), cr = lane >> 3, ch = lane & 7;
            const char* wsrc = reinterpret_cast<const char*>(prm.w + (size_t)(2 * r0 * kD + c0 + cr) * kD + d0 + ch * 8);
            const uint32_t wdst = sb + X_BYTES + r0 * 2048 + cr * 128, sw = (ch ^ cr) << 4;
            if (tid == 160) {
                asm volatile("prefetch.tensormap [%0];" ::"l"(&mapX) : "memory");
                asm volatile("prefetch.tensormap [%0];" ::"l"(&mapWo) : "memory");
                asm volatile("prefetch.tensormap [%0];" ::"l"(&mapWe) : "memory");
            }
            bar_sync(4 + wq, wq == 5 ? 160 : 64);
#pragma unroll
            for (int k = 0; k < 8; k++) {
                const int t = k >> 2, i = k & 3;
                cp_async16(wdst + t * 2048 + i * 512 + (sw ^ ((i & 1) << 6)), wsrc + (size_t)t * (2 * kD * kD * 2) + i * (4 * kD * 2), true);
            }
            asm volatile("cp.async.commit_group;" ::: "memory");
            if (wq < 7) bar_arrive(5 + wq, 64);
        } else if (lane == 0) {
#pragma unroll
            for (int s = 0; s < kStages; s++) { mbar_init(bar_full + 8 * s, 1); mbar_init(bar_empty + 8 * s, 4); }
            mbar_init(bar_rx, 1);
            mbar_init(bar_rx + 8, 1);
            asm volatile("fence.mbarrier_init.release.cluster;" ::: "memory");
            mbar_arrive(bar_full);
#pragma unroll
            for (int u = 1; u < kStages; u++) mbar_expect_tx(bar_full + 8 * u, X_BYTES + ((u & 1) ? 7 : 8) * 2048);
            mbar_expect_tx(bar_rx, 8192);
            tma_4d(sb + STAGE_BYTES, &mapX, bar_full + 8, c0, 1, l0, b);
            tma_3d(sb + STAGE_BYTES + X_BYTES, &mapWo, bar_full + 8, d0, c0, 0);
        }
    } else {
        const int row = tid >> 1, half = tid & 1;
        const char* xsrc = reinterpret_cast<const char*>(prm.x + (size_t)(b * kT + 2 * (l0 + row)) * kD + c0 + half * 8);
        const uint32_t xdst = sb + row * 32 + ((half ^ ((row >> 2) & 1)) << 4);
        const int crow = tid >> 3, ch = tid & 7;
        const char* wsrc = reinterpret_cast<const char*>(prm.w + (size_t)(c0 + crow) * kD + d0 + ch * 8);
        const uint32_t wdst = sb + X_BYTES + crow * 128 + ((ch ^ (crow & 7)) << 4);
        cp_async16(wdst, wsrc, true);
#pragma unroll
        for (int i = 0; i < 3; i++) cp_async16(xdst + i * 64 * 32, xsrc + (size_t)i * (64 * 2 * kD * 2), true);
        const bool ok = l0 + row + 192 < kT / 2;
        cp_async16(xdst + 192 * 32, ok ? xsrc + (size_t)3 * (64 * 2 * kD * 2) : xsrc, ok);
        cp_async16(wdst + 2048, wsrc + (size_t)(2 * kD * kD * 2), true);
        asm volatile("cp.async.commit_group;" ::: "memory");
        bar_arrive(9, 160);
    }
    __syncwarp();
    const int warp = __shfl_sync(0xffffffffu, tid >> 5, 0);
    asm volatile("barrier.cluster.arrive.relaxed.aligned;" ::: "memory");

    uint32_t a_rx = 0, a_bar = 0, a_stm = 0, a_ld = 0, rdst = 0, rbar = 0, a_frag = 0;
    int nvalid = 0, orow = 0, l6 = 0, lead = 0;
    uint4* p_slot = nullptr; const uint4* p_gather = nullptr; __nv_bfloat16* p_out = nullptr; uint4* gdst = nullptr;
    if (warp < 4) {
        uint4* const gs = prm.stat + ((size_t)(blockIdx.x >> 3) * 4 + warp) * 64;
        p_slot = pin(gs + (blockIdx.x & 7) * 8 + (lane >> 2)); p_gather = pin(gs + (lane & 3) * 8 + (lane >> 2));
        p_out = pin(prm.out + (size_t)(b * kL + l0 + 64 * q + (tid >> 3)) * kD + d0 + (tid & 7) * 8);
        a_rx = pin(sb + OFF_RX + tid * 16); a_bar = pin(bar_rx);
        a_stm = pin(sb + OFF_STG + (((tid >> 4) & 1) * 8 + (tid & 7)) * 128 + (((((tid >> 5) << 1) | ((tid >> 3) & 1)) ^ (tid & 7)) << 4));
        a_ld = pin(sb + OFF_STG + (tid >> 3) * 128 + (((tid ^ (tid >> 3)) & 7) << 4));
        nvalid = pin(min(kN, kL - l0) - 64 * q); orow = pin(tid >> 3); l6 = pin(48 + 2 * (lane & 3)); lead = pin(lane & 3);
        asm volatile("mapa.shared::cluster.u32 %0, %1, %2;" : "=r"(rdst) : "r"(sb + OFF_RX + tid * 16), "r"((q ^ 1) & 1));
        asm volatile("mapa.shared::cluster.u32 %0, %1, %2;" : "=r"(rbar) : "r"(bar_rx), "r"((q ^ 1) & 1));
        gdst = pin(prm.part + (size_t)((blockIdx.x & ~3) + ((q & 2) ^ 2)) * 1024 + (q & 1) * 512 + tid);
        a_frag = pin(sb + kStage0 * STAGE_BYTES + X_BYTES + ((lane & 7) + 8 * (lane >> 4)) * 128 + (((2 * warp + ((lane >> 3) & 1)) ^ (lane & 7)) << 4));
    }

    if (warp == 4) {
        bar_arrive(3, 192);
        if (lane == 0) {
            const uint32_t t_start = (uint32_t)clock();
#pragma unroll 1
            for (int u = 2; u < kUnits; u++) {
                const int s = u & 7, p = u & 1, c = c0 + (u >> 1) * 16;
                const uint32_t bar = bar_full + 8 * s, dst = sb + s * STAGE_BYTES;
                if (u < kStages) {
                    while ((uint32_t)clock() - t_start < (uint32_t)(kPace0 + (u - 2) * kPace)) {}
                } else {
                    mbar_wait(bar_empty + 8 * s, 0);
                    mbar_expect_tx(bar, X_BYTES + (p ? 7 : 8) * 2048);
                }
                tma_4d(dst, &mapX, bar, c, p, l0, b);
                tma_3d(dst + X_BYTES, p ? &mapWo : &mapWe, bar, d0, c, 0);
            }
        }
        __syncwarp();
    } else {
        asm volatile("cp.async.wait_group 0;" ::: "memory");
        asm volatile("fence.proxy.async.shared::cta;" ::: "memory");
        if (warp < 4) bar_sync(8, 128);
        else bar_arrive(warp == 5 ? 3 : 6 + warp, warp == 5 ? 192 : 160);
    }

    const int t128 = tid & 127;
    uint4* const xa = reinterpret_cast<uint4*>(smem + OFF_XA) + t128;
    float* const misc = reinterpret_cast<float*>(smem + OFF_MISC);

    if (warp >= 4) {
        if (warp == 5) {
            const float g0 = __bfloat162float(prm.gamma[d0 + lane]), g1 = __bfloat162float(prm.gamma[d0 + 32 + lane]);
            const float b0 = __bfloat162float(prm.beta[d0 + lane]), b1 = __bfloat162float(prm.beta[d0 + 32 + lane]);
            const unsigned int e = prm.epoch[blockIdx.x] + 1;
            misc[lane] = g0; misc[32 + lane] = g1; misc[64 + lane] = b0; misc[96 + lane] = b1;
            if (lane == 0) { misc[128] = __uint_as_float(e); prm.epoch[blockIdx.x] = e; }
        }
        asm volatile("barrier.cluster.wait.aligned;" ::: "memory");
        bar_sync(5, 256);
        const uint32_t par = pin(__float_as_uint(misc[128]) & 1);
        bar_sync(6, 256);
        const uint4* slot = prm.part + (size_t)blockIdx.x * 1024;
        if (t128 == 0) {
            mbar_expect_tx(bar_rx + 8, 16384);
            asm volatile("cp.async.bulk.shared::cluster.global.mbarrier::complete_tx::bytes [%0], [%1], %2, [%3];"
                         ::"r"(sb + OFF_SLOT), "l"(slot), "r"(16384), "r"(bar_rx + 8) : "memory");
        }
        mbar_wait(bar_rx + 8, 0);
        uint4 m[8];
#pragma unroll
        for (int k = 0; k < 8; k++) m[k] = reinterpret_cast<const uint4*>(smem + OFF_SLOT)[k * 128 + t128];
        uint32_t bad = 0;
#pragma unroll
        for (int k = 0; k < 8; k++) bad |= msg_bad(m[k], par);
        if (bad & 1) {
            uint32_t it = 0;
            do {
                bad = 0;
#pragma unroll
                for (int k = 0; k < 8; k++) if (msg_bad(m[k], par) & 1) m[k] = ld_msg(slot + k * 128 + t128);
#pragma unroll
                for (int k = 0; k < 8; k++) bad |= msg_bad(m[k], par);
                if (++it > kSpinLimit) __trap();
            } while (bad & 1);
        }
#pragma unroll
        for (int k = 0; k < 4; k++)
            xa[k * 128] = make_uint4(add2(m[k].x, m[4 + k].x), add2(m[k].y, m[4 + k].y), add2(m[k].z, m[4 + k].z), add2(m[k].w, m[4 + k].w));
        bar_arrive(1, 256);
        return;
    }

    float v[32];
    uint32_t par;
    float hg0, hg1, hb0, hb1;
    {
        float lo[64], hi[64];
        const uint64_t descX0 = prm.descB + ((sb & 0x3FFFF) >> 4);
        const uint64_t descW0 = prm.descA + (((sb + X_BYTES) & 0x3FFFF) >> 4);
        wg_fence();
#pragma unroll 1
        for (int it = 0; it < kMainIters; it++) {
            const uint32_t s = (2 * it) & 7;
            const uint64_t da = descW0 + ((s * STAGE_BYTES) >> 4), db = descX0 + ((s * STAGE_BYTES) >> 4);
            const uint32_t ph = (it >> 2) & 1;
            static_for<0, 8>([&](auto R) {
                constexpr int r = decltype(R)::value;
                if constexpr (r == 0) { wgmma_n128s<0, 0>(lo, da, db, it != 0); wgmma_n120s<0, 128 * 32>(hi, da, db, it != 0); }
                else { wgmma_n128i<r * 2048, r * 32>(lo, da, db); wgmma_n120i<r * 2048, r * 32 + 128 * 32>(hi, da, db); }
                if (r == 1) {
                    wg_commit(); wg_wait<1>();
                    if (it != 0 && lane == 0) mbar_arrive(bar_empty + 8 * ((s + 7) & 7));
                }
                if (it == 0) {
                    if (r == 1) bar_sync(3, 192);
                    if (r == 3) bar_sync(12, 160);
                    if (r == 5) bar_sync(13, 160);
                }
                if ((r == 4 && it != 0) || (r == 7 && it == 0)) mbar_wait(bar_full + 8 * (s + 1), ph);
            });
            wg_commit();
            static_for<0, 7>([&](auto R) {
                constexpr int r = decltype(R)::value;
                wgmma_n128i<STAGE_BYTES + r * 2048, STAGE_BYTES + r * 32>(lo, da, db); wgmma_n120i<STAGE_BYTES + r * 2048, STAGE_BYTES + r * 32 + 128 * 32>(hi, da, db);
                if (r == 1) {
                    wg_commit(); wg_wait<1>();
                    if (lane == 0) mbar_arrive(bar_empty + 8 * s);
                }
                if (r == 3) mbar_wait(bar_full + 8 * ((s + 2) & 7), ((it + 1) >> 2) & 1);
            });
            wg_commit();
        }
        asm volatile("barrier.cluster.wait.aligned;" ::: "memory");
        bar_sync(5, 256);
        par = pin(__float_as_uint(misc[128]) & 1);
        if (lead == 0) st_msg(p_slot, 0, 0, 0, 0, par ^ 1);
        const uint64_t da0 = descW0 + ((kStage0 * STAGE_BYTES) >> 4), db0 = descX0 + ((kStage0 * STAGE_BYTES) >> 4);
        const uint64_t dbC[4] = {fresh<5>(db0), fresh<6>(db0), fresh<7>(db0), fresh<8>(db0)};
        const uint64_t daA[2] = {fresh<1>(da0), fresh<2>(da0)}, dbA[2] = {fresh<1>(db0), fresh<2>(db0)};
        const uint64_t daB[2] = {fresh<3>(da0), fresh<4>(da0)}, dbB[2] = {fresh<3>(db0), fresh<4>(db0)};
        { const int dr = warp * 16 + (lane >> 2);
          hg0 = 0.5f * misc[dr]; hg1 = 0.5f * misc[dr + 8]; hb0 = 0.5f * misc[64 + dr]; hb1 = 0.5f * misc[64 + dr + 8]; }
        uint32_t af[kRs][4];
        float o[32];
#define TAIL(OWNH, OTHA, OWNA, QA, QB)                                                                                     \
        tail_ab1<OWNH>(OTHA, OWNA, af, daA[OWNH], dbA[OWNH], daB[OWNH], dbB[OWNH], bar_full, a_frag, gdst, par);                                             \
        if (q == QA) {                                                                                                     \
            tail_b23<QA>(OWNA, af, o, dbC[QA], rdst, rbar);                                                                    \
            finish_sums<QA == 3 ? 7 : 8>(o, v, xa);                                                                        \
        } else {                                                                                                           \
            tail_b23<QB>(OWNA, af, o, dbC[QB], rdst, rbar);                                                                    \
            finish_sums<QB == 3 ? 7 : 8>(o, v, xa);                                                                        \
        }
        if (q < 2) { TAIL(0, hi, lo, 0, 1) } else { TAIL(1, lo, hi, 2, 3) }
    }
    mbar_wait_peer(a_bar, 0);
#pragma unroll
    for (int k = 0; k < 4; k++) {
        uint4 r;
        asm volatile("ld.shared.v4.u32 {%0, %1, %2, %3}, [%4];" : "=r"(r.x), "=r"(r.y), "=r"(r.z), "=r"(r.w) : "r"(a_rx + k * 2048));
        v[8 * k] += bf_lo(r.x); v[8 * k + 1] += bf_hi(r.x); v[8 * k + 2] += bf_lo(r.y); v[8 * k + 3] += bf_hi(r.y);
        v[8 * k + 4] += bf_lo(r.z); v[8 * k + 5] += bf_hi(r.z); v[8 * k + 6] += bf_lo(r.w); v[8 * k + 7] += bf_hi(r.w);
    }

    float ga0, ga1, be0, be1;
    {
        const float m0 = l6 < nvalid ? v[24] : 0.f, m1 = l6 + 1 < nvalid ? v[25] : 0.f;
        const float m2 = l6 < nvalid ? v[26] : 0.f, m3 = l6 + 1 < nvalid ? v[27] : 0.f;
        float s0 = m0 + m1, s1 = m2 + m3, q0 = fmaf(m0, m0, m1 * m1), q1 = fmaf(m2, m2, m3 * m3);
        float s0b = v[1], s1b = v[3], q0b = v[1] * v[1], q1b = v[3] * v[3];
        s0 += v[0]; s1 += v[2]; q0 = fmaf(v[0], v[0], q0); q1 = fmaf(v[2], v[2], q1);
#pragma unroll
        for (int c = 1; c < 8; c++) {
            if (c == 6) continue;
            s0 += v[4 * c]; s0b += v[4 * c + 1]; q0 = fmaf(v[4 * c], v[4 * c], q0); q0b = fmaf(v[4 * c + 1], v[4 * c + 1], q0b);
            s1 += v[4 * c + 2]; s1b += v[4 * c + 3]; q1 = fmaf(v[4 * c + 2], v[4 * c + 2], q1); q1b = fmaf(v[4 * c + 3], v[4 * c + 3], q1b);
        }
        s0 += s0b; s1 += s1b; q0 += q0b; q1 += q1b;
#pragma unroll
        for (int o = 1; o <= 2; o <<= 1) {
            s0 += __shfl_xor_sync(~0u, s0, o); q0 += __shfl_xor_sync(~0u, q0, o);
            s1 += __shfl_xor_sync(~0u, s1, o); q1 += __shfl_xor_sync(~0u, q1, o);
        }
        if (lead == 0) st_msg(p_slot, __float_as_uint(s0), __float_as_uint(q0), __float_as_uint(s1), __float_as_uint(q1), par);
        const uint32_t t_sent = (uint32_t)clock();
        while ((uint32_t)clock() - t_sent < kPollDelay) {}
        uint4 t0 = ld_msg(p_gather), t1 = ld_msg(p_gather + 32);
        uint32_t it = 0;
        while ((msg_bad(t0, par) | msg_bad(t1, par)) & 1) {
            t0 = ld_msg(p_gather); t1 = ld_msg(p_gather + 32);
            if (++it > kSpinLimit) __trap();
        }
        __syncwarp();
        s0 = __uint_as_float(t0.x) + __uint_as_float(t1.x); q0 = __uint_as_float(t0.y) + __uint_as_float(t1.y);
        s1 = __uint_as_float(t0.z) + __uint_as_float(t1.z); q1 = __uint_as_float(t0.w) + __uint_as_float(t1.w);
#pragma unroll
        for (int o = 1; o <= 2; o <<= 1) {
            s0 += __shfl_xor_sync(~0u, s0, o); q0 += __shfl_xor_sync(~0u, q0, o);
            s1 += __shfl_xor_sync(~0u, s1, o); q1 += __shfl_xor_sync(~0u, q1, o);
        }
        const float inv = 1.0f / kL;
        const float mu0 = s0 * inv, mu1 = s1 * inv;
        ga0 = hg0 * rsqrt_fast(fmaxf(fmaf(-mu0, mu0, q0 * inv), 0.f) + 1e-5f);
        ga1 = hg1 * rsqrt_fast(fmaxf(fmaf(-mu1, mu1, q1 * inv), 0.f) + 1e-5f);
        be0 = fmaf(-mu0, ga0, hb0); be1 = fmaf(-mu1, ga1, hb1);
    }
    {
        auto store = [&](int i) {
            bar_sync(2, 128);
            uint4 val;
            asm volatile("ld.shared.v4.u32 {%0, %1, %2, %3}, [%4];" : "=r"(val.x), "=r"(val.y), "=r"(val.z), "=r"(val.w) : "r"(a_ld + i * 2048) : "memory");
            if (orow + 16 * i < nvalid)
                asm volatile("st.global.v4.u32 [%0], {%1, %2, %3, %4};" ::"l"(p_out + (size_t)i * 16 * kD), "r"(val.x), "r"(val.y), "r"(val.z), "r"(val.w) : "memory");
        };
#pragma unroll
        for (int i = 0; i < 4; i++) {
            uint32_t pk[4];
#pragma unroll
            for (int k = 0; k < 2; k++) {
                const int c = 2 * i + k;
                pk[2 * k] = pack2(gelu_tanh_half(fmaf(v[4 * c], ga0, be0)), gelu_tanh_half(fmaf(v[4 * c + 1], ga0, be0)));
                pk[2 * k + 1] = pack2(gelu_tanh_half(fmaf(v[4 * c + 2], ga1, be1)), gelu_tanh_half(fmaf(v[4 * c + 3], ga1, be1)));
            }
            if (i > 0) store(i - 1);
            asm volatile("stmatrix.sync.aligned.m8n8.x4.trans.shared.b16 [%0], {%1, %2, %3, %4};" ::"r"(a_stm + i * 2048),
                         "r"(pk[0]), "r"(pk[1]), "r"(pk[2]), "r"(pk[3]) : "memory");
        }
        store(3);
    }
}

typedef CUresult (*EncodeFn)(CUtensorMap*, CUtensorMapDataType, cuuint32_t, void*, const cuuint64_t*, const cuuint64_t*,
                             const cuuint32_t*, const cuuint32_t*, CUtensorMapInterleave, CUtensorMapSwizzle,
                             CUtensorMapL2promotion, CUtensorMapFloatOOBfill);

}

extern "C" void kernel_launch(void* const* d_in, const int* in_sizes, int n_in, void* d_out, int out_size) {
    const __nv_bfloat16* x = (const __nv_bfloat16*)d_in[0];
    const __nv_bfloat16* w = (const __nv_bfloat16*)d_in[1];
    static EncodeFn enc = nullptr;
    static Params prm;
    if (!enc) {
        void* fn = nullptr;
        cudaDriverEntryPointQueryResult st;
        cudaGetDriverEntryPoint("cuTensorMapEncodeTiled", &fn, cudaEnableDefault, &st);
        enc = (EncodeFn)fn;
        cudaFuncSetAttribute(conv_stem_kernel, cudaFuncAttributeMaxDynamicSharedMemorySize, SMEM_BYTES);
        void* p;
        cudaGetSymbolAddress(&p, g_part); prm.part = (uint4*)p;
        cudaGetSymbolAddress(&p, g_stat); prm.stat = (uint4*)p;
        cudaGetSymbolAddress(&p, g_epoch); prm.epoch = (unsigned int*)p;
    }
    prm.x = x; prm.w = w;
    prm.descA = (64ull << 16) | (64ull << 32) | (1ull << 62);
    prm.descB = (1ull << 16) | (16ull << 32) | (3ull << 62);
    prm.gamma = (const __nv_bfloat16*)d_in[2]; prm.beta = (const __nv_bfloat16*)d_in[3];
    prm.out = (__nv_bfloat16*)d_out;
    CUtensorMap mapX, mapWe, mapWo;
    {
        cuuint64_t dims[4] = {(cuuint64_t)kD, 2, (cuuint64_t)(kT / 2), (cuuint64_t)kB};
        cuuint64_t strides[3] = {(cuuint64_t)kD * 2, (cuuint64_t)kD * 4, (cuuint64_t)kT * kD * 2};
        cuuint32_t box[4] = {16, 1, 256, 1};
        cuuint32_t es[4] = {1, 1, 1, 1};
        enc(&mapX, CU_TENSOR_MAP_DATA_TYPE_BFLOAT16, 4, (void*)x, dims, strides, box, es, CU_TENSOR_MAP_INTERLEAVE_NONE,
            CU_TENSOR_MAP_SWIZZLE_32B, CU_TENSOR_MAP_L2_PROMOTION_L2_128B, CU_TENSOR_MAP_FLOAT_OOB_FILL_NONE);
    }
    for (int p = 0; p < 2; p++) {
        cuuint64_t dims[3] = {(cuuint64_t)kD, (cuuint64_t)kD, (cuuint64_t)(p ? 7 : 8)};
        cuuint64_t strides[2] = {(cuuint64_t)kD * 2, (cuuint64_t)kD * kD * 4};
        cuuint32_t box[3] = {64, 16, (cuuint32_t)(p ? 7 : 8)};
        cuuint32_t es[3] = {1, 1, 1};
        enc(p ? &mapWo : &mapWe, CU_TENSOR_MAP_DATA_TYPE_BFLOAT16, 3, (void*)(w + (size_t)p * kD * kD), dims, strides, box, es,
            CU_TENSOR_MAP_INTERLEAVE_NONE, CU_TENSOR_MAP_SWIZZLE_128B, CU_TENSOR_MAP_L2_PROMOTION_L2_128B, CU_TENSOR_MAP_FLOAT_OOB_FILL_NONE);
    }
    conv_stem_kernel<<<128, kThreads, SMEM_BYTES, cudaStreamPerThread>>>(prm, mapX, mapWe, mapWo);
}
```
